```python
import torch

def _softmax(x, axis=-1):
    return torch.softmax(x, dim=axis)

def _gelu(x):
    return torch.nn.functional.gelu(x, approximate='tanh')

def _silu(x):
    return torch.nn.functional.silu(x)

def _sigmoid(x):
    return torch.sigmoid(x)

def _layernorm(x, axis=-1, eps=1e-05):
    m = x.mean(dim=axis, keepdim=True)
    v = x.var(dim=axis, keepdim=True, unbiased=False)
    return (x - m) / torch.sqrt(v + eps)

def _scatter_add(tgt, idx, src, axis=0):
    return tgt.clone().index_add_(axis, idx, src)

def _segment_sum(src, seg, n):
    out = torch.zeros((n,) + src.shape[1:], dtype=src.dtype)
    return out.index_add_(0, seg, src)

def _pad(x, pw):
    flat = tuple((v for pair in reversed(pw) for v in pair))
    return torch.nn.functional.pad(x, flat)
kernel_name = 'gated_mix__linear_attn_block__mixer_gmlp__prompt'

def setup_inputs():

    _w = lambda a: (lambda t: t.to(torch.bfloat16) if t.is_floating_point() else t)(torch.as_tensor(a))

    def _A_setup():
        B, S, D = (1, 2048, 512)
        return {'x': _w((lambda *s: torch.randn(*s, dtype=torch.bfloat16) * 0.05)(B, S, D)), 'wqkv': _w((lambda *s: torch.randn(*s, dtype=torch.bfloat16) * 1.6)(D, 3 * D)), 'wo': _w((lambda *s: torch.randn(*s, dtype=torch.bfloat16) * 0.2)(D, D))}
    _A_in = _A_setup()

    def _B_setup():
        B, S, D, F = (1, 2048, 512, 1792)
        Fh = F // 2
        return {'x': _w((lambda *s: torch.randn(*s, dtype=torch.bfloat16) * 0.05)(B, S, D)), 'w_in': _w((lambda *s: torch.randn(*s, dtype=torch.bfloat16) * 0.4)(D, 2 * Fh)), 'w_sp': _w(0.01 * (lambda *s: torch.randn(*s, dtype=torch.bfloat16) * 0.4)(S, S)), 'b_sp': _w(1.0 + 0.01 * (lambda *s: torch.randn(*s, dtype=torch.bfloat16) * 0.05)(S)), 'w_out': _w((lambda *s: torch.randn(*s, dtype=torch.bfloat16) * 0.05)(Fh, D))}
    _B_in = _B_setup()
    return {'A_x': _A_in['x'], 'A_wqkv': _A_in['wqkv'], 'A_wo': _A_in['wo'], 'B_x': _B_in['x'], 'B_w_in': _B_in['w_in'], 'B_w_sp': _B_in['w_sp'], 'B_b_sp': _B_in['b_sp'], 'B_w_out': _B_in['w_out'], 'gate_w': _w((lambda *s: torch.randn(*s, dtype=torch.bfloat16) * 0.05)(512) * 16.0)}

def reference(A_x, A_wqkv, A_wo, B_x, B_w_in, B_w_sp, B_b_sp, B_w_out, gate_w):

    def _A_ref(x, wqkv, wo):
        B, S, D = x.shape
        H = 32
        Dh = D // H
        qkv = (lambda x, *d: x.permute(*d))((x @ wqkv).reshape(B, S, 3, H, Dh), 2, 0, 3, 1, 4)
        q, k, v = (qkv[0], qkv[1], qkv[2])
        phi = lambda t: torch.where(t > 0, t + 1, torch.exp(t)) + 1e-06
        pq, pk = (phi(q), phi(k))
        kv = torch.einsum('bhsd,bhse->bhde', pk, v)
        z = torch.einsum('bhsd->bhd', pk)
        num = torch.einsum('bhqd,bhde->bhqe', pq, kv)
        den = torch.einsum('bhqd,bhd->bhq', pq, z)[..., None] + 1e-06
        o = num / den
        return (lambda x, *d: x.permute(*d))(o, 0, 2, 1, 3).reshape(B, S, D) @ wo

    def _B_ref(x, w_in, w_sp, b_sp, w_out):
        B, S, D = x.shape
        F = w_in.shape[-1]
        Fh = F // 2
        z = _gelu(torch.einsum('bsd,df->bsf', x, w_in))
        z1 = z[..., :Fh].clone()
        z2 = _layernorm(z[..., Fh:], axis=-1)
        g = torch.einsum('ts,bsf->btf', w_sp, z2) + b_sp[None, :, None]
        return torch.einsum('bsf,fd->bsd', z1 * g, w_out)
    x = A_x
    g = _sigmoid((x * gate_w).sum(-1, keepdims=True))
    a = _A_ref(x, A_wqkv, A_wo)
    b = _B_ref(x, B_w_in, B_w_sp, B_b_sp, B_w_out)
    return g * a + (1 - g) * b
```

```cpp
#include <cuda_runtime.h>
#include <cuda.h>
#include <cuda_bf16.h>
#include <stdint.h>

namespace {

__device__ __align__(1024) uint8_t g_z2t[8 * 32 * 14336];
__device__ __align__(1024) uint4 g_of[32 * 32 * 128];
__device__ __align__(1024) uint4 g_yf[32 * 56 * 128];
__device__ __align__(1024) uint2 g_stats[2048 * 8];
__device__ __align__(1024) float g_kv[2 * 8 * 1088];
__device__ __align__(1024) float g_gate[2048];
constexpr int C_START = 0, C_Z2 = 1, C_KV = 9, C_G = 17, C_Y = 33, C_NUM = 49;
__device__ __align__(1024) unsigned g_cnt[C_NUM * 32];
#define GT(id) do { } while (0)
#define TS(id) do { } while (0)

constexpr uint32_t SLOT = 16384;
constexpr uint32_t OFF_STG = 12 * SLOT;
constexpr uint32_t OFF_KV = OFF_STG + 28672;
constexpr uint32_t OFF_ST = OFF_KV + 4352;
constexpr uint32_t OFF_BAR = OFF_ST + 512;
constexpr uint32_t SMEM_USED = OFF_BAR + 94 * 8;
constexpr uint32_t SMEM_BYTES = 232448;
static_assert(SMEM_USED <= SMEM_BYTES && OFF_STG + 2 * SLOT <= OFF_BAR, "smem");
constexpr uint32_t SB = 1024;

__device__ __forceinline__ uint32_t p2stage(int i) { return ((0x532410u >> (4 * i)) & 15u) * (2 * SLOT); }

__device__ __forceinline__ int p3idx(int u) { return (int)((0x10543105432ull >> (4 * u)) & 15u); }
__device__ __forceinline__ uint32_t yslot(int j) { return ((j & 2) ? p2stage(2) : OFF_STG) + (j & 1) * SLOT; }

enum {
  B_XF = 0,
  B_E1 = 8,
  B_F2 = 12,
  B_E2 = 18,
  B_Z2D = 24, B_KVD = 25, B_Z2D1 = 26,
  B_SF1 = 27,
  B_Z2R = 28,
  B_EP = 29, B_KVB = 30,
  B_F1 = 31,
  B_HO = 59,
  B_F3 = 64,
  B_FA = 75,
  B_EA = 82,
  B_YR = 86, B_GD = 87, B_GR = 88,
  B_SS = 89,
  B_RN = 91,
  B_NUM = 93,
  W_EPOCH = 93
};

__device__ __forceinline__ uint32_t smem_u32(const void* p) { return (uint32_t)__cvta_generic_to_shared(p); }
__device__ __forceinline__ void mbar_init(uint32_t a, uint32_t c) { asm volatile("mbarrier.init.shared::cta.b64 [%0], %1;" ::"r"(a), "r"(c) : "memory"); }
__device__ __forceinline__ void mbar_expect(uint32_t a, uint32_t b) { asm volatile("mbarrier.arrive.expect_tx.shared::cta.b64 _, [%0], %1;" ::"r"(a), "r"(b) : "memory"); }
__device__ __forceinline__ void mbar_arrive(uint32_t a) { asm volatile("mbarrier.arrive.shared::cta.b64 _, [%0];" ::"r"(a) : "memory"); }
constexpr uint32_t SPIN_LIMIT = 1u << 22;
#define TIMEOUT(code) __trap()
__device__ __forceinline__ void mbar_wait(uint32_t a, uint32_t par) {
  asm volatile("{ .reg .pred p; .reg .u32 n; mov.u32 n, 0;\n"
               "W: mbarrier.try_wait.parity.shared::cta.b64 p, [%0], %1; @p bra D;\n"
               "add.u32 n, n, 1; setp.lt.u32 p, n, 0x40000; @p bra W; trap;\nD: }" ::"r"(a), "r"(par) : "memory");
}
__device__ __forceinline__ void tma2d(uint32_t dst, const CUtensorMap* m, int c0, int c1, uint32_t bar) {
  asm volatile("cp.async.bulk.tensor.2d.shared::cluster.global.mbarrier::complete_tx::bytes [%0], [%1, {%2, %3}], [%4];" ::"r"(dst), "l"(m), "r"(c0), "r"(c1), "r"(bar) : "memory");
}
__device__ __forceinline__ bool stale8(const uint32_t* f, uint32_t tag) {
  uint32_t a, b, c, d;
  asm("lop3.b32 %0, %1, %2, %3, 0x7e;" : "=r"(a) : "r"(f[0]), "r"(f[4]), "r"(tag));
  asm("lop3.b32 %0, %1, %2, %3, 0x7e;" : "=r"(b) : "r"(f[8]), "r"(f[12]), "r"(tag));
  asm("lop3.b32 %0, %1, %2, %3, 0x7e;" : "=r"(c) : "r"(f[16]), "r"(f[20]), "r"(tag));
  asm("lop3.b32 %0, %1, %2, %3, 0x7e;" : "=r"(d) : "r"(f[24]), "r"(f[28]), "r"(tag));
  asm("lop3.b32 %0, %1, %2, %3, 0xfe;" : "=r"(a) : "r"(a), "r"(b), "r"(c));
  return (a | d) & 1;
}
__device__ __forceinline__ void st_tagged(uint4* p, uint32_t r0, uint32_t r1, uint32_t r2, uint32_t r3, uint32_t tag) {
  asm volatile("{ .reg .b128 t; mov.b128 t, {%1,%2,%3,%4}; st.relaxed.gpu.global.b128 [%0], t; }" ::"l"(p), "r"((r0 & ~1u) | tag), "r"(r1), "r"(r2), "r"(r3) : "memory");
}
__device__ __forceinline__ void ld_frag(uint32_t* r, const uint4* p) {
  asm volatile("{ .reg .b128 t; ld.relaxed.gpu.global.b128 t, [%4]; mov.b128 {%0,%1,%2,%3}, t; }" : "=r"(r[0]), "=r"(r[1]), "=r"(r[2]), "=r"(r[3]) : "l"(p) : "memory");
}
__device__ __forceinline__ void bulk_ld(uint32_t dst, const void* src, uint32_t bytes, uint32_t bar) {
  asm volatile("cp.async.bulk.shared::cluster.global.mbarrier::complete_tx::bytes [%0], [%1], %2, [%3];" ::"r"(dst), "l"(src), "r"(bytes), "r"(bar) : "memory");
}
__device__ __forceinline__ void bulk_st(void* dst, uint32_t src, uint32_t bytes) {
  asm volatile("cp.async.bulk.global.shared::cta.bulk_group [%0], [%1], %2;" ::"l"(dst), "r"(src), "r"(bytes) : "memory");
}
__device__ __forceinline__ void bulk_red_f32(void* dst, uint32_t src, uint32_t bytes) {
  asm volatile("cp.reduce.async.bulk.global.shared::cta.bulk_group.add.f32 [%0], [%1], %2;" ::"l"(dst), "r"(src), "r"(bytes) : "memory");
}
__device__ __forceinline__ void bulk_commit() { asm volatile("cp.async.bulk.commit_group;" ::: "memory"); }
__device__ __forceinline__ void bulk_wait() { asm volatile("cp.async.bulk.wait_group 0;" ::: "memory"); }
__device__ __forceinline__ void l2_prefetch(const void* p, uint32_t bytes) { asm volatile("cp.async.bulk.prefetch.L2.global [%0], %1;" ::"l"(p), "r"(bytes) : "memory"); }
__device__ __forceinline__ void fence_async_smem() { asm volatile("fence.proxy.async.shared::cta;" ::: "memory"); }
__device__ __forceinline__ void publish(int word) {
  asm volatile("red.release.gpu.global.add.u32 [%0], 1;" ::"l"(g_cnt + word) : "memory");
}
__device__ __forceinline__ void poll(int c, uint32_t target) {
  uint32_t v, n = 0;
  while (true) {
    asm volatile("ld.acquire.gpu.global.u32 %0, [%1];" : "=r"(v) : "l"(g_cnt + c * 32) : "memory");
    if ((int)(v - target) >= 0) break;
    if (++n > SPIN_LIMIT) TIMEOUT(10000 + c);
  }
  asm volatile("fence.proxy.async.global;" ::: "memory");
}
__device__ __forceinline__ void wg_fence() { asm volatile("wgmma.fence.sync.aligned;" ::: "memory"); }
__device__ __forceinline__ void wg_commit() { asm volatile("wgmma.commit_group.sync.aligned;" ::: "memory"); }
template <int N> __device__ __forceinline__ void wg_wait() { asm volatile("wgmma.wait_group.sync.aligned %0;" ::"n"(N) : "memory"); }
template <int N> __device__ __forceinline__ void reg_fence(float (&d)[N]) {
#pragma unroll
  for (int i = 0; i < N; i++) asm volatile("" : "+f"(d[i])::"memory");
}
__device__ __forceinline__ void named_bar(int id, int n) { asm volatile("bar.sync %0, %1;" ::"r"(id), "r"(n) : "memory"); }
__device__ __forceinline__ uint64_t mk64(uint32_t lo, uint32_t hi) { uint64_t r; asm("mov.b64 %0, {%1, %2};" : "=l"(r) : "r"(lo), "r"(hi)); return r; }
__device__ __forceinline__ uint64_t desc_k128(uint32_t a) { return mk64(((SB + a) >> 4) + (1u << 16), 64u | (1u << 30)); }
__device__ __forceinline__ uint64_t desc_n128(uint32_t a) { return mk64(((SB + a) >> 4) + (512u << 16), 64u | (1u << 30)); }
__device__ __forceinline__ uint64_t desc_n128w(uint32_t a) { return mk64(((SB + a) >> 4) + (1024u << 16), 64u | (1u << 30)); }

__device__ __forceinline__ uint64_t desc_k0(uint32_t a) { return mk64(((SB + a) >> 4) + (8u << 16), 16u); }
__device__ __forceinline__ uint32_t pack_bf16(float lo, float hi) { uint32_t r; asm("cvt.rn.bf16x2.f32 %0, %1, %2;" : "=r"(r) : "f"(hi), "f"(lo)); return r; }
__device__ __forceinline__ float bf_lo(uint32_t v) { return __uint_as_float(v << 16); }
__device__ __forceinline__ float bf_hi(uint32_t v) { return __uint_as_float(v & 0xffff0000u); }
__device__ __forceinline__ uint32_t hmul2(uint32_t a, uint32_t b) { uint32_t r; asm("mul.rn.bf16x2 %0, %1, %2;" : "=r"(r) : "r"(a), "r"(b)); return r; }
__device__ __forceinline__ uint32_t hfma2(uint32_t a, uint32_t b, uint32_t c) { uint32_t r; asm("fma.rn.bf16x2 %0, %1, %2, %3;" : "=r"(r) : "r"(a), "r"(b), "r"(c)); return r; }
__device__ __forceinline__ uint32_t ymul(float s0, float s1, uint32_t h, uint32_t bh, uint32_t z) { return hmul2(hfma2(pack_bf16(s0, s1), h, bh), z); }
__device__ __forceinline__ void stsm4(uint32_t a, uint32_t r0, uint32_t r1, uint32_t r2, uint32_t r3) {
  asm volatile("stmatrix.sync.aligned.m8n8.x4.shared.b16 [%0], {%1,%2,%3,%4};" ::"r"(a), "r"(r0), "r"(r1), "r"(r2), "r"(r3) : "memory");
}
__device__ __forceinline__ void stsm4t(uint32_t a, uint32_t r0, uint32_t r1, uint32_t r2, uint32_t r3) {
  asm volatile("stmatrix.sync.aligned.m8n8.x4.trans.shared.b16 [%0], {%1,%2,%3,%4};" ::"r"(a), "r"(r0), "r"(r1), "r"(r2), "r"(r3) : "memory");
}
__device__ __forceinline__ void sts128(uint32_t a, uint32_t r0, uint32_t r1, uint32_t r2, uint32_t r3) {
  asm volatile("st.shared.v4.b32 [%0], {%1,%2,%3,%4};" ::"r"(a), "r"(r0), "r"(r1), "r"(r2), "r"(r3) : "memory");
}
__device__ __forceinline__ uint4 lds128(uint32_t a) {
  uint4 v; asm volatile("ld.shared.v4.b32 {%0,%1,%2,%3}, [%4];" : "=r"(v.x), "=r"(v.y), "=r"(v.z), "=r"(v.w) : "r"(a) : "memory"); return v;
}
__device__ __forceinline__ uint4 ldg_cg128(const void* p) {
  uint4 v; asm volatile("ld.global.cg.v4.b32 {%0,%1,%2,%3}, [%4];" : "=r"(v.x), "=r"(v.y), "=r"(v.z), "=r"(v.w) : "l"(p) : "memory"); return v;
}
__device__ __forceinline__ float ldg_cg32f(const void* p) { float v; asm volatile("ld.global.cg.f32 %0, [%1];" : "=f"(v) : "l"(p) : "memory"); return v; }
__device__ __forceinline__ float rcp_fast(float x) { float r; asm("rcp.approx.ftz.f32 %0, %1;" : "=f"(r) : "f"(x)); return r; }
__device__ __forceinline__ float gelu2(float x) {
  float w = x * fmaf(x * x, 0.0356774081f, 0.7978845608f), t;
  asm("tanh.approx.f32 %0, %1;" : "=f"(t) : "f"(w));
  return fmaf(x, t, x);
}
__device__ __forceinline__ uint32_t phi2(float t0, float t1) {
  float e0, e1;
  asm("ex2.approx.ftz.f32 %0, %1;" : "=f"(e0) : "f"(t0 * 1.4426950409f));
  asm("ex2.approx.ftz.f32 %0, %1;" : "=f"(e1) : "f"(t1 * 1.4426950409f));
  uint32_t r;
  asm("{ .reg .b32 e, t;\n"
      "min.bf16x2 e, %1, %3; add.rn.bf16x2 e, e, %4; max.bf16x2 t, %2, %5; add.rn.bf16x2 %0, t, e; }"
      : "=r"(r) : "r"(pack_bf16(e0, e1)), "r"(pack_bf16(t0, t1)), "r"(0x3f803f80u), "r"(0x35863586u), "r"(0u));
  return r;
}

__device__ __forceinline__ void wgmma_n128_rs(float (&d)[64], uint32_t a0, uint32_t a1, uint32_t a2, uint32_t a3, uint64_t b, int sd) {
  asm volatile(
    "{ .reg .pred p; setp.ne.b32 p, %69, 0;\n"
    "wgmma.mma_async.sync.aligned.m64n128k16.f32.bf16.bf16 {%0, %1, %2, %3, %4, %5, %6, %7, %8, %9, %10, %11, %12, %13, %14, %15, %16, %17, %18, %19, %20, %21, %22, %23, %24, %25, %26, %27, %28, %29, %30, %31, %32, %33, %34, %35, %36, %37, %38, %39, %40, %41, %42, %43, %44, %45, %46, %47, %48, %49, %50, %51, %52, %53, %54, %55, %56, %57, %58, %59, %60, %61, %62, %63}, {%64, %65, %66, %67}, %68, p, 1, 1, 1; }"
    : "+f"(d[0]), "+f"(d[1]), "+f"(d[2]), "+f"(d[3]), "+f"(d[4]), "+f"(d[5]), "+f"(d[6]), "+f"(d[7]), "+f"(d[8]), "+f"(d[9]), "+f"(d[10]), "+f"(d[11]), "+f"(d[12]), "+f"(d[13]), "+f"(d[14]), "+f"(d[15]), "+f"(d[16]), "+f"(d[17]), "+f"(d[18]), "+f"(d[19]), "+f"(d[20]), "+f"(d[21]), "+f"(d[22]), "+f"(d[23]), "+f"(d[24]), "+f"(d[25]), "+f"(d[26]), "+f"(d[27]), "+f"(d[28]), "+f"(d[29]), "+f"(d[30]), "+f"(d[31]), "+f"(d[32]), "+f"(d[33]), "+f"(d[34]), "+f"(d[35]), "+f"(d[36]), "+f"(d[37]), "+f"(d[38]), "+f"(d[39]), "+f"(d[40]), "+f"(d[41]), "+f"(d[42]), "+f"(d[43]), "+f"(d[44]), "+f"(d[45]), "+f"(d[46]), "+f"(d[47]), "+f"(d[48]), "+f"(d[49]), "+f"(d[50]), "+f"(d[51]), "+f"(d[52]), "+f"(d[53]), "+f"(d[54]), "+f"(d[55]), "+f"(d[56]), "+f"(d[57]), "+f"(d[58]), "+f"(d[59]), "+f"(d[60]), "+f"(d[61]), "+f"(d[62]), "+f"(d[63])
    : "r"(a0), "r"(a1), "r"(a2), "r"(a3), "l"(b), "r"(sd));
}

__device__ __forceinline__ void wgmma_n72_rs(float (&d)[36], uint32_t a0, uint32_t a1, uint32_t a2, uint32_t a3, uint64_t b, int sd) {
  asm volatile(
    "{ .reg .pred p; setp.ne.b32 p, %41, 0;\n"
    "wgmma.mma_async.sync.aligned.m64n72k16.f32.bf16.bf16 {%0, %1, %2, %3, %4, %5, %6, %7, %8, %9, %10, %11, %12, %13, %14, %15, %16, %17, %18, %19, %20, %21, %22, %23, %24, %25, %26, %27, %28, %29, %30, %31, %32, %33, %34, %35}, {%36, %37, %38, %39}, %40, p, 1, 1, 0; }"
    : "+f"(d[0]), "+f"(d[1]), "+f"(d[2]), "+f"(d[3]), "+f"(d[4]), "+f"(d[5]), "+f"(d[6]), "+f"(d[7]), "+f"(d[8]), "+f"(d[9]), "+f"(d[10]), "+f"(d[11]), "+f"(d[12]), "+f"(d[13]), "+f"(d[14]), "+f"(d[15]), "+f"(d[16]), "+f"(d[17]), "+f"(d[18]), "+f"(d[19]), "+f"(d[20]), "+f"(d[21]), "+f"(d[22]), "+f"(d[23]), "+f"(d[24]), "+f"(d[25]), "+f"(d[26]), "+f"(d[27]), "+f"(d[28]), "+f"(d[29]), "+f"(d[30]), "+f"(d[31]), "+f"(d[32]), "+f"(d[33]), "+f"(d[34]), "+f"(d[35])
    : "r"(a0), "r"(a1), "r"(a2), "r"(a3), "l"(b), "r"(sd));
}

__device__ __forceinline__ void wgmma_n24_z(float (&d)[12], uint64_t a, uint64_t b) {
  asm volatile(
    "{ .reg .pred p; setp.ne.b32 p, 0, 0;\n"
    "wgmma.mma_async.sync.aligned.m64n24k16.f32.bf16.bf16 {%0, %1, %2, %3, %4, %5, %6, %7, %8, %9, %10, %11}, %12, %13, p, 1, 1, 0, 0; }"
    : "=f"(d[0]), "=f"(d[1]), "=f"(d[2]), "=f"(d[3]), "=f"(d[4]), "=f"(d[5]), "=f"(d[6]), "=f"(d[7]), "=f"(d[8]), "=f"(d[9]), "=f"(d[10]), "=f"(d[11])
    : "l"(a), "l"(b));
}

template <int TA, int TB>
__device__ __forceinline__ void wgmma_n112(float (&d)[56], uint64_t a, uint64_t b, int sd) {
  asm volatile(
    "{ .reg .pred p; setp.ne.b32 p, %58, 0;\n"
    "wgmma.mma_async.sync.aligned.m64n112k16.f32.bf16.bf16 {"
    "%0, %1, %2, %3, %4, %5, %6, %7, %8, %9, %10, %11, %12, %13, %14, %15, %16, %17, %18, %19, %20, %21, %22, %23, %24, %25, %26, %27, %28, %29, %30, %31, "
    "%32, %33, %34, %35, %36, %37, %38, %39, %40, %41, %42, %43, %44, %45, %46, %47, %48, %49, %50, %51, %52, %53, %54, %55 "
    "}, %56, %57, p, 1, 1, %59, %60; }"
    : "+f"(d[0]), "+f"(d[1]), "+f"(d[2]), "+f"(d[3]), "+f"(d[4]), "+f"(d[5]), "+f"(d[6]), "+f"(d[7]), "+f"(d[8]), "+f"(d[9]), "+f"(d[10]), "+f"(d[11]),
      "+f"(d[12]), "+f"(d[13]), "+f"(d[14]), "+f"(d[15]), "+f"(d[16]), "+f"(d[17]), "+f"(d[18]), "+f"(d[19]), "+f"(d[20]), "+f"(d[21]), "+f"(d[22]),
      "+f"(d[23]), "+f"(d[24]), "+f"(d[25]), "+f"(d[26]), "+f"(d[27]), "+f"(d[28]), "+f"(d[29]), "+f"(d[30]), "+f"(d[31]), "+f"(d[32]), "+f"(d[33]),
      "+f"(d[34]), "+f"(d[35]), "+f"(d[36]), "+f"(d[37]), "+f"(d[38]), "+f"(d[39]), "+f"(d[40]), "+f"(d[41]), "+f"(d[42]), "+f"(d[43]), "+f"(d[44]),
      "+f"(d[45]), "+f"(d[46]), "+f"(d[47]), "+f"(d[48]), "+f"(d[49]), "+f"(d[50]), "+f"(d[51]), "+f"(d[52]), "+f"(d[53]), "+f"(d[54]), "+f"(d[55])
    : "l"(a), "l"(b), "r"(sd), "n"(TA), "n"(TB));
}

template <int TA, int TB>
__device__ __forceinline__ void wgmma_n128(float (&d)[64], uint64_t a, uint64_t b, int sd) {
  asm volatile(
    "{ .reg .pred p; setp.ne.b32 p, %66, 0;\n"
    "wgmma.mma_async.sync.aligned.m64n128k16.f32.bf16.bf16 {"
    "%0, %1, %2, %3, %4, %5, %6, %7, %8, %9, %10, %11, %12, %13, %14, %15, %16, %17, %18, %19, %20, %21, %22, %23, %24, %25, %26, %27, %28, %29, %30, %31, "
    "%32, %33, %34, %35, %36, %37, %38, %39, %40, %41, %42, %43, %44, %45, %46, %47, %48, %49, %50, %51, %52, %53, %54, %55, %56, %57, %58, %59, %60, %61, "
    "%62, %63 "
    "}, %64, %65, p, 1, 1, %67, %68; }"
    : "+f"(d[0]), "+f"(d[1]), "+f"(d[2]), "+f"(d[3]), "+f"(d[4]), "+f"(d[5]), "+f"(d[6]), "+f"(d[7]), "+f"(d[8]), "+f"(d[9]), "+f"(d[10]), "+f"(d[11]),
      "+f"(d[12]), "+f"(d[13]), "+f"(d[14]), "+f"(d[15]), "+f"(d[16]), "+f"(d[17]), "+f"(d[18]), "+f"(d[19]), "+f"(d[20]), "+f"(d[21]), "+f"(d[22]),
      "+f"(d[23]), "+f"(d[24]), "+f"(d[25]), "+f"(d[26]), "+f"(d[27]), "+f"(d[28]), "+f"(d[29]), "+f"(d[30]), "+f"(d[31]), "+f"(d[32]), "+f"(d[33]),
      "+f"(d[34]), "+f"(d[35]), "+f"(d[36]), "+f"(d[37]), "+f"(d[38]), "+f"(d[39]), "+f"(d[40]), "+f"(d[41]), "+f"(d[42]), "+f"(d[43]), "+f"(d[44]),
      "+f"(d[45]), "+f"(d[46]), "+f"(d[47]), "+f"(d[48]), "+f"(d[49]), "+f"(d[50]), "+f"(d[51]), "+f"(d[52]), "+f"(d[53]), "+f"(d[54]), "+f"(d[55]),
      "+f"(d[56]), "+f"(d[57]), "+f"(d[58]), "+f"(d[59]), "+f"(d[60]), "+f"(d[61]), "+f"(d[62]), "+f"(d[63])
    : "l"(a), "l"(b), "r"(sd), "n"(TA), "n"(TB));
}

template <int V> struct IC { __device__ constexpr operator int() const { return V; } };

struct Params {
  const __nv_bfloat16* x;
  const __nv_bfloat16* gate_w;
  const __nv_bfloat16* b_sp;
  const __nv_bfloat16* w_sp;
  const __nv_bfloat16* w_in;
  const __nv_bfloat16* wqkv;
  const __nv_bfloat16* wo;
  const __nv_bfloat16* w_out;
  __nv_bfloat16* out;
};

#define A_GAP 280
#define FO_K 18
#define HINT_J 1
#define BDELAY_U 7
#define GATE_C 3
#define ST_WAIT 200
template <int N, typename F>
__device__ __forceinline__ void p1_tile(float (&a0)[N / 2], float (&a1)[N / 2], int n0, uint32_t bars, bool el, int handover, uint32_t lbo, F mm) {
#pragma unroll 1
  for (int c = 0; c < 8; c++) {
    const int n = n0 + c;
    mbar_wait(bars + 8 * (B_F1 + n), 0);
    if (n0 == 0) mbar_wait(bars + 8 * (B_XF + c), 0);
    if (el) TS(64 + n);
    const uint32_t xa = c * SLOT, ra = (8 + (c & 3)) * SLOT;
    reg_fence(a0); reg_fence(a1);
    wg_fence();
#pragma unroll
    for (int kk = 0; kk < 4; kk++) {
      if (N == 128) {
        mm(a0, desc_n128(ra + kk * 2048), desc_k128(xa + kk * 32), kk != 0 || c != 0);
        mm(a1, desc_n128(ra + 8192 + kk * 2048), desc_k128(xa + kk * 32), kk != 0 || c != 0);
      } else {
        const uint64_t db = mk64(((SB + ra + kk * 2048) >> 4) + lbo, 64u | (1u << 30));
        mm(a0, desc_k128(xa + kk * 32), db, kk != 0 || c != 0);
        mm(a1, desc_k128(xa + 8192 + kk * 32), db, kk != 0 || c != 0);
      }
      if (kk == 0) {
        wg_commit();
        wg_wait<1>();
        if (el && c > 0) mbar_arrive(bars + 8 * (B_E1 + ((c - 1) & 3)));
      }
    }
    wg_commit();
  }
  if (el) mbar_arrive(bars + 8 * handover);
  wg_wait<0>();
  reg_fence(a0); reg_fence(a1);
  if (el) mbar_arrive(bars + 8 * (B_E1 + 3));
}

#define ST_CHUNK 2048

__global__ void __launch_bounds__(384, 1)
fused_kernel(const __grid_constant__ CUtensorMap tm_x, const __grid_constant__ CUtensorMap tm_win, const __grid_constant__ CUtensorMap tm_wqkv,
             const __grid_constant__ CUtensorMap tm_wsp, const __grid_constant__ CUtensorMap tm_wo, const __grid_constant__ CUtensorMap tm_wout,
             const __grid_constant__ CUtensorMap tm_wout2,
             const Params p) {
  extern __shared__ __align__(1024) uint8_t smem_raw[];
  const uint32_t sb = smem_u32(smem_raw);
  const uint32_t bars = sb + OFF_BAR;
  if (threadIdx.x == 256) TS(0);
  if (threadIdx.x == 0) asm volatile("prefetch.tensormap [%0];" ::"l"(&tm_x) : "memory");
  if (threadIdx.x == 32) asm volatile("prefetch.tensormap [%0];" ::"l"(&tm_win) : "memory");
  if (sb != SB) __trap();
  const uint32_t stg = sb + OFF_STG;
  const int tid = threadIdx.x, lane = tid & 31;
  const int warp = __shfl_sync(0xffffffffu, tid >> 5, 0);

  int id = blockIdx.x;
  if (gridDim.x == 132) {
    uint32_t smid;
    asm volatile("mov.u32 %0, %%smid;" : "=r"(smid));
    if (smid >= 132) __trap();
    const int t = smid >> 1;
    const int gq = t < 32 ? t & 7 : t < 60 ? 1 + (t - 32) % 7 : 0;
    const int ix = t < 32 ? t >> 3 : t < 60 ? 4 + (t - 32) / 7 : t - 58;
    if (t == 60 || t == 61) {
      if (tid == 0) {
        uint32_t v, n = 0;
        asm volatile("atom.relaxed.gpu.global.add.u32 %0, [%1], 1;" : "=r"(v) : "l"(g_cnt + C_START * 32) : "memory");
        const uint32_t target = (v / 132 + 1) * 132;
        do {
          __nanosleep(200);
          asm volatile("ld.relaxed.gpu.global.u32 %0, [%1];" : "=r"(v) : "l"(g_cnt + C_START * 32) : "memory");
        } while ((int)(v - target) < 0 && ++n < SPIN_LIMIT);
      }
      return;
    }
    id = gq * 16 + ix * 2 + (smid & 1);
  }
  const int rb = (id >> 5) * 4 + ((id >> 2) & 3), sl = ((id >> 4) & 1) * 4 + (id & 3);
  const int r64 = rb * 2 + ((id >> 4) & 1), db = id & 3;

  const int zoff = (sl & 3) == 3 ? 16 : 0, zd = 512 - 16 * sl - zoff;
  auto init_range = [&](auto lo, auto hi) {
#pragma unroll
    for (int j = lo; j < hi; j++)
      mbar_init(bars + 8 * j, (j >= B_Z2D && j <= B_Z2D1) || (j >= B_EA && j < B_EA + 4) || j == B_GD || j == B_SS || j == B_SS + 1 ? 4 : j == B_SF1 || j >= B_RN ? 2 : 1);
  };
  if (warp == 4) {
    if (lane == 0) {
      TS(240);
      init_range(IC<B_XF>(), IC<B_XF + 8>());
      init_range(IC<B_F1>(), IC<B_F1 + 4>());
      fence_async_smem();
      TS(241);
    }
    __syncwarp();
    asm volatile("bar.arrive 0, 384;" ::: "memory");
    if (lane == 0) {
#pragma unroll 1
      for (int c = 0; c < 8; c++) {
        mbar_expect(bars + 8 * (B_XF + c), 16384);
        tma2d(sb + c * SLOT, &tm_x, 64 * c, 128 * rb, bars + 8 * (B_XF + c));
        if (c == 0) TS(242);
        if (c < 4) {
          mbar_expect(bars + 8 * (B_F1 + c), 16384);
          tma2d(sb + (8 + c) * SLOT, &tm_win, 896 + 64 * sl, 64 * c, bars + 8 * (B_F1 + c));
          tma2d(sb + (8 + c) * SLOT + 8192, &tm_win, 896 + 64 * sl + zd, 64 * c, bars + 8 * (B_F1 + c));
          TS(160 + c);
        }
      }
    }
    __syncwarp();
  } else {
    if (tid == 160 || tid == 192) {
      if (tid == 160) { init_range(IC<B_XF + 8>(), IC<B_F1>()); init_range(IC<B_F3>(), IC<B_NUM>()); }
      else init_range(IC<B_F1 + 4>(), IC<B_F3>());
      fence_async_smem();
      TS(243 + (tid == 192));
    }
    __syncwarp();
    named_bar(0, 384);
  }

  if (warp >= 8) {
    asm volatile("setmaxnreg.dec.sync.aligned.u32 40;");
    auto store_z2 = [&](int m) {
        mbar_wait(bars + 8 * (B_Z2D + 2 * m), 0);
#pragma unroll 1
        for (uint32_t o = 0; o < 14336; o += ST_CHUNK) {
          bulk_st(g_z2t + (size_t)(sl * 32 + rb * 2 + m) * 14336 + o, stg + m * 14336 + o, ST_CHUNK);
          bulk_commit();
          bulk_wait();
        }
        mbar_arrive(bars + 8 * B_SF1);
        TS(19 + m);
        publish((C_Z2 + sl) * 32);
        TS(8 + 3 * m);
    };
    if (warp == 8) {
      if (lane == 0) {
        TS(1);
        asm volatile("prefetch.tensormap [%0];" ::"l"(&tm_wqkv) : "memory");
        asm volatile("prefetch.tensormap [%0];" ::"l"(&tm_wsp) : "memory");
        asm volatile("prefetch.tensormap [%0];" ::"l"(&tm_wo) : "memory");
        asm volatile("prefetch.tensormap [%0];" ::"l"(&tm_wout) : "memory");
        asm volatile("prefetch.tensormap [%0];" ::"l"(&tm_wout2) : "memory");
      }
      __syncwarp();
      {
        const CUtensorMap* tm = &tm_win;
        int c0 = 896 + 64 * sl, d0 = zd, c1 = 256, s1 = 64, d1 = 0;
#pragma unroll 1
        for (int n = 4; n < 28; n++) {
          if ((n & 7) == 0) {
            tm = n == 16 ? &tm_win : &tm_wqkv;
            c0 = n == 8 ? 512 + 64 * sl : 64 * sl;
            d0 = n == 8 ? 512 : n == 16 ? zd : 0;
            c1 = 0; s1 = n == 24 ? 128 : 64; d1 = n == 24 ? 64 : 0;
          }
          const uint32_t f = bars + 8 * (B_F1 + n), dst = sb + (8 + (n & 3)) * SLOT;
          mbar_wait(bars + 8 * (B_E1 + (n & 3)), ((n >> 2) - 1) & 1);
          asm volatile("{ .reg .pred p; elect.sync _|p, 0xffffffff;\n"
                       "@p mbarrier.arrive.expect_tx.shared::cta.b64 _, [%1], 16384;\n"
                       "@p cp.async.bulk.tensor.2d.shared::cluster.global.mbarrier::complete_tx::bytes [%0], [%2, {%3, %4}], [%1];\n"
                       "@p cp.async.bulk.tensor.2d.shared::cluster.global.mbarrier::complete_tx::bytes [%0 + 8192], [%2, {%5, %6}], [%1]; }"
                       ::"r"(dst), "r"(f), "l"(tm), "r"(c0), "r"(c1), "r"(c0 + d0), "r"(c1 + d1) : "memory");
          if (lane == 0) TS(160 + n);
          c1 += s1;
        }
      }
      {
        mbar_wait(bars + 8 * B_E1, 0);
        mbar_wait(bars + 8 * B_Z2R, 0);
        asm volatile("fence.proxy.async.global;" ::: "memory");
        if (lane == 0) TS(3);
        int i = 0, ph = 1;
        const uint8_t* zsrc = g_z2t + (size_t)sl * 32 * 14336;
#pragma unroll 1
        for (int k = 0; k < 32; k++) {
          const uint32_t f = bars + 8 * (B_F2 + i), st = sb + p2stage(i);
          if (k >= 6 || k == 1 || k == 3 || k == 4) mbar_wait(bars + 8 * (k >= 6 ? B_E2 + i : B_E1 + (k < 2 ? k : k - 1)), k >= 6 ? ph : 0);
          asm volatile("{ .reg .pred p; elect.sync _|p, 0xffffffff;\n"
                       "@p mbarrier.arrive.expect_tx.shared::cta.b64 _, [%1], 30720;\n"
                       "@p cp.async.bulk.tensor.2d.shared::cluster.global.mbarrier::complete_tx::bytes [%0], [%2, {%3, %4}], [%1];\n"
                       "@p cp.async.bulk.shared::cluster.global.mbarrier::complete_tx::bytes [%0 + 16384], [%5], 14336, [%1]; }"
                       ::"r"(st), "r"(f), "l"(&tm_wsp), "r"(64 * k), "r"(128 * rb), "l"(zsrc) : "memory");
          if (lane == 0 && k < 16) TS(192 + k);
          zsrc += 14336;
          if (++i == 6) { i = 0; ph ^= 1; }
        }
#pragma unroll 1
        for (int u = 0; u < 11; u++) {
          const int is = p3idx(u);
          if (u == BDELAY_U) mbar_wait(bars + 8 * B_FA, 0);
          const uint32_t f = bars + 8 * (B_F3 + u), st = sb + p2stage(is);
          const CUtensorMap* tm = u < 4 ? &tm_wo : u < 8 ? &tm_wout : &tm_wout2;
          const int r0 = u < 4 ? 0 : 16 * (u & 3), r1 = u < 4 ? 8 * u : 0;
          mbar_wait(bars + 8 * (B_E2 + is), (0x1f0 >> u) & 1);
          asm volatile("{ .reg .pred p; elect.sync _|p, 0xffffffff;\n"
                       "@p mbarrier.arrive.expect_tx.shared::cta.b64 _, [%1], 32768;\n"
                       "@p cp.async.bulk.tensor.3d.shared::cluster.global.mbarrier::complete_tx::bytes [%0], [%2, {%3, %5, %6}], [%1];\n"
                       "@p cp.async.bulk.tensor.3d.shared::cluster.global.mbarrier::complete_tx::bytes [%0 + 16384], [%2, {%4, %5, %6}], [%1]; }"
                       ::"r"(st), "r"(f), "l"(tm), "r"(128 * db), "r"(128 * db + 64), "r"(r0), "r"(r1) : "memory");
          if (lane == 0) TS(208 + u);
        }
        if (lane == 0) TS(7);
      }
    } else if (warp < 11) {
      const int m = warp - 9;
      mbar_wait(bars + 8 * B_EP, 0);
      uint32_t ep;
      asm volatile("ld.shared.u32 %0, [%1];" : "=r"(ep) : "r"(bars + 8 * W_EPOCH) : "memory");
      float* kv = g_kv + ((ep & 1) * 8 + sl) * 1088;
#pragma unroll 1
      for (int b = 0; b < 2; b++) {
        mbar_wait(bars + 8 * (B_SS + b), 0);
        __nanosleep(ST_WAIT);
        const uint2* sp = g_stats + (rb * 8 + (lane >> 4) * 4) * 128 + b * 64 + m * 32 + (lane & 15) * 2;
        uint4 v[4];
        uint32_t spins = 0;
        while (true) {
          uint32_t bad = 0;
#pragma unroll
          for (int j = 0; j < 4; j++)
            asm volatile("ld.relaxed.gpu.global.v2.b64 {%0, %1}, [%2];" : "=l"(*reinterpret_cast<uint64_t*>(&v[j].x)), "=l"(*reinterpret_cast<uint64_t*>(&v[j].z)) : "l"(sp + j * 128) : "memory");
#pragma unroll
          for (int j = 0; j < 4; j++) bad |= (v[j].x ^ ep) | (v[j].z ^ ep);
          if (!__any_sync(0xffffffffu, (bad & 7) != 0)) break;
          if (++spins > SPIN_LIMIT) TIMEOUT(20000);
        }
        const bool odd = lane & 16;
        const float s0 = (__uint_as_float(v[0].x) + __uint_as_float(v[1].x)) + (__uint_as_float(v[2].x) + __uint_as_float(v[3].x));
        const float q0 = (__uint_as_float(v[0].y) + __uint_as_float(v[1].y)) + (__uint_as_float(v[2].y) + __uint_as_float(v[3].y));
        const float s1 = (__uint_as_float(v[0].z) + __uint_as_float(v[1].z)) + (__uint_as_float(v[2].z) + __uint_as_float(v[3].z));
        const float q1 = (__uint_as_float(v[0].w) + __uint_as_float(v[1].w)) + (__uint_as_float(v[2].w) + __uint_as_float(v[3].w));
        const float mean = ((odd ? s1 : s0) + __shfl_xor_sync(0xffffffffu, odd ? s0 : s1, 16)) * (1.f / 896.f);
        const float msq = ((odd ? q1 : q0) + __shfl_xor_sync(0xffffffffu, odd ? q0 : q1, 16)) * (1.f / 896.f);
        const float rstd = rsqrtf(fmaxf(fmaf(-mean, mean, msq), 0.f) + 4e-5f);
        asm volatile("st.shared.u32 [%0], %1;" ::"r"(sb + OFF_ST + (b * 64 + m * 32 + (lane & 15) * 2 + (lane >> 4)) * 4), "r"(pack_bf16(rstd, -mean * bf_lo(pack_bf16(rstd, 0.f)))) : "memory");
        __syncwarp();
        if (lane == 0) { mbar_arrive(bars + 8 * (B_RN + b)); if (!m) TS(4 + b); }
      }
      if (lane == 0) {
        if (m) {
          store_z2(1);
          mbar_wait(bars + 8 * B_KVD, 0);
          bulk_red_f32(kv, sb + OFF_KV, 4352);
          bulk_commit();
          bulk_wait();
          publish((C_KV + sl) * 32);
          TS(12);
          poll(C_KV + sl, ep * 16);
          mbar_arrive(bars + 8 * B_KVB);
        } else {
          poll(C_Z2 + sl, ep * 32);
          mbar_arrive(bars + 8 * B_Z2R);
          mbar_wait(bars + 8 * (B_EA + 3), 0);
          poll(C_Y + rb, ep * 32);
          TS(10);
#pragma unroll 1
          for (int j = 0; j < 7; j++) {
            if (j == 0) mbar_wait(bars + 8 * B_YR, 0);
            if (j >= 4) mbar_wait(bars + 8 * (B_EA + j - 4), 0);
            mbar_expect(bars + 8 * (B_FA + j), 16384);
            bulk_ld(sb + yslot(j), g_yf + (r64 * 56 + j * 8) * 128, 16384, bars + 8 * (B_FA + j));
            TS(224 + j);
            if (j == 1 || j == 2) __nanosleep(A_GAP);
          }
        }
      }
    } else {
      if (lane < 2) l2_prefetch(p.w_in + (size_t)(256 + id * 2 + lane) * 1792 + 896, 1792);
      uint32_t ep = 0;
      if (lane == 0) {
        asm volatile("atom.relaxed.gpu.global.add.u32 %0, [%1], 1;" : "=r"(ep) : "l"(g_cnt + C_START * 32) : "memory");
        ep = ep / gridDim.x + 1;
        asm volatile("st.shared.u32 [%0], %1;" ::"r"(bars + 8 * W_EPOCH), "r"(ep) : "memory");
        mbar_arrive(bars + 8 * B_EP);
      }
      ep = __shfl_sync(0xffffffffu, ep, 0);
      if (lane < 17) reinterpret_cast<float4*>(g_kv + ((ep + 1) & 1) * 8 * 1088)[id * 17 + lane] = make_float4(0.f, 0.f, 0.f, 0.f);
      if (lane < 8) l2_prefetch(lane < 4 ? p.wqkv + (size_t)(id * 4 + lane) * 1536 : p.w_in + (size_t)(id * 4 + lane - 4) * 1792, lane < 4 ? 3072 : 1792);
      mbar_wait(bars + 8 * B_GD, 0);
      if (lane == 0) { publish((C_G + rb) * 32); TS(14); }
      __syncwarp();
      if (lane < 11) l2_prefetch(lane < 4 ? p.wo + (size_t)(id * 4 + lane) * 512 : p.w_out + (size_t)(id * 7 + lane - 4) * 512, 1024);
      if (lane == 0) {
        TS(60);
        poll(C_G + rb, ep * 8);
        mbar_arrive(bars + 8 * B_GR);
        store_z2(0);
      }
    }
  } else {
    if (warp >= 4) named_bar(2, 128);
    asm volatile("setmaxnreg.inc.sync.aligned.u32 232;");
    const int w = warp & 3, t128 = tid & 127;
    const bool el = t128 == 0;
    const int g = lane >> 2, q = lane & 3;
    const uint32_t tbase = stg + ((lane >> 4) * 8 + (lane & 7)) * 128 + (((2 * w + ((lane >> 3) & 1)) ^ (lane & 7)) << 4);
    const int srow = w * 16 + ((lane >> 3) & 1) * 8 + (lane & 7);
    uint32_t ep = 0;
    float co[64];
    if (warp < 4) {
      if (el) TS(31);
      float a0[56], a1[56];
      float gv[4];
      uint32_t bv[4];
      uint32_t z0[28], z1[28];
#pragma unroll 1
      for (int t = 0; t < 2; t++) {
        p1_tile<112>(a0, a1, 16 * t, bars, el, B_HO + 2 * t, (512u + (zoff >> 3)) << 16,
                     [](float (&d)[56], uint64_t a, uint64_t b, int sd) { wgmma_n112<0, 1>(d, a, b, sd); });
        if (el) { TS(16 + 16 * t); if (t == 0) GT(252); }
        if (t == 1) {
          mbar_wait(bars + 8 * B_GR, 0);
          const int row0 = rb * 128 + w * 16 + g;
#pragma unroll
          for (int i = 0; i < 4; i++) { gv[i] = ldg_cg32f(g_gate + row0 + (i >> 1) * 64 + (i & 1) * 8); bv[i] = reinterpret_cast<const unsigned short*>(p.b_sp)[row0 + (i >> 1) * 64 + (i & 1) * 8]; }
        }
        if (t == 0) {
          mbar_wait(bars + 8 * B_EP, 0);
          asm volatile("ld.shared.u32 %0, [%1];" : "=r"(ep) : "r"(bars + 8 * W_EPOCH) : "memory");
        }
        if (t == 1) {
#pragma unroll
          for (int i = 0; i < 28; i++) z0[i] = pack_bf16(gelu2(a0[2 * i]), gelu2(a0[2 * i + 1]));
#pragma unroll
          for (int i = 0; i < 28; i++) z1[i] = pack_bf16(gelu2(a1[2 * i]), gelu2(a1[2 * i + 1]));
        } else {
          auto gelu_block = [&](float (&a)[56], uint32_t (&zz)[28], int m) {
            float s0 = 0.f, s1 = 0.f, q0 = 0.f, q1 = 0.f;
#pragma unroll
            for (int i = 0; i < 56; i += 4) {
              const float v0 = gelu2(a[i]), v1 = gelu2(a[i + 1]), v2 = gelu2(a[i + 2]), v3 = gelu2(a[i + 3]);
              s0 += v0 + v1; q0 = fmaf(v0, v0, q0); q0 = fmaf(v1, v1, q0);
              s1 += v2 + v3; q1 = fmaf(v2, v2, q1); q1 = fmaf(v3, v3, q1);
              zz[i / 2] = pack_bf16(v0, v1); zz[i / 2 + 1] = pack_bf16(v2, v3);
            }
            const bool o1 = q & 1;
            float u0 = o1 ? s1 : s0, u1 = o1 ? q1 : q0;
            u0 += __shfl_xor_sync(0xffffffffu, o1 ? s0 : s1, 1);
            u1 += __shfl_xor_sync(0xffffffffu, o1 ? q0 : q1, 1);
            u0 += __shfl_xor_sync(0xffffffffu, u0, 2);
            u1 += __shfl_xor_sync(0xffffffffu, u1, 2);
            if (q < 2)
              asm volatile("st.relaxed.gpu.global.b64 [%0], %1;" ::"l"(g_stats + (rb * 8 + sl) * 128 + m * 64 + w * 16 + g + q * 8),
                           "l"(mk64((__float_as_uint(u0) & ~7u) | (ep & 7), __float_as_uint(u1))) : "memory");
            if (lane == 0) mbar_arrive(bars + 8 * (B_SS + m));
            if (el) TS(23 + 2 * m);
          };
          gelu_block(a0, z0, 0);
          gelu_block(a1, z1, 1);
        }
        if (el) TS(17 + 16 * t);
        if (t == 1) break;
#pragma unroll
        for (int m = 0; m < 2; m++) {
          if (m) mbar_wait(bars + 8 * (B_HO + 1), 0);
          mbar_wait(bars + 8 * (B_RN + m), 0);
          if (el) TS(49 + 7 * m);
          uint32_t x0, x1;
          asm volatile("ld.shared.u32 %0, [%1];" : "=r"(x0) : "r"(sb + OFF_ST + (m * 64 + w * 16 + g) * 4) : "memory");
          asm volatile("ld.shared.u32 %0, [%1];" : "=r"(x1) : "r"(sb + OFF_ST + (m * 64 + w * 16 + g + 8) * 4) : "memory");
          const uint32_t r0 = __byte_perm(x0, 0, 0x1010), n0 = __byte_perm(x0, 0, 0x3232), r1 = __byte_perm(x1, 0, 0x1010), n1 = __byte_perm(x1, 0, 0x3232);
#pragma unroll
          for (int i = 0; i < 28; i += 4)
            stsm4t(tbase + m * 14336 + (i / 4) * 2048, hfma2(z0[i], r0, n0), hfma2(z0[i + 1], r1, n1), hfma2(z0[i + 2], r0, n0), hfma2(z0[i + 3], r1, n1));
          fence_async_smem();
          __syncwarp();
          if (lane == 0) mbar_arrive(bars + 8 * (B_Z2D + 2 * m));
#pragma unroll
          for (int i = 0; i < 28; i++) z0[i] = z1[i];
        }
        if (el) TS(57);
      }
      float (&c0)[56] = a0, (&c1)[56] = a1;
      uint32_t hh[4], bh[4];
#pragma unroll
      for (int i = 0; i < 4; i++) { hh[i] = pack_bf16(0.5f - 0.5f * gv[i], 0.5f - 0.5f * gv[i]); bh[i] = pack_bf16(bf_lo(bv[i]) * bf_lo(hh[i]), bf_lo(bv[i]) * bf_lo(hh[i])); asm volatile("" : "+r"(hh[i]), "+r"(bh[i])); }
      if (el) { TS(34); GT(253); }
      {
        int i = 0, ph = 0, pi = 0;
#pragma unroll 1
        for (int k = 0; k < 32; k++) {
          mbar_wait(bars + 8 * (B_F2 + i), ph);
          if (el) TS(96 + k);
          const uint32_t st = p2stage(i);
          reg_fence(c0); reg_fence(c1);
          wg_fence();
#pragma unroll
          for (int kk = 0; kk < 4; kk++) {
            const uint64_t dbb = desc_k128(st + SLOT + kk * 32);
            wgmma_n112<0, 0>(c0, desc_k128(st + kk * 32), dbb, kk != 0 || k != 0);
            wgmma_n112<0, 0>(c1, desc_k128(st + 8192 + kk * 32), dbb, kk != 0 || k != 0);
            if (kk == 0) {
              wg_commit();
              wg_wait<1>();
              if (el && k > 0) mbar_arrive(bars + 8 * (B_E2 + pi));
            }
          }
          wg_commit();
          if (el && k == FO_K) mbar_arrive(bars + 8 * (B_HO + 3));
          pi = i;
          if (++i == 6) { i = 0; ph ^= 1; }
        }
        wg_wait<0>();
        reg_fence(c0); reg_fence(c1);
        if (el) mbar_arrive(bars + 8 * (B_E2 + pi));
      }
      if (el) { TS(35); GT(254); }
      if (lane == 0) asm volatile("red.relaxed.gpu.global.add.u32 [%0], 1;" ::"l"(g_cnt + (C_Y + rb) * 32) : "memory");
      uint4* dst = g_yf + (rb * 2 * 56 + sl) * 128 + t128;
#pragma unroll
      for (int j = 0; j < 7; j++) {
        st_tagged(dst + j * 1024, ymul(c0[8 * j], c0[8 * j + 1], hh[0], bh[0], z0[4 * j]), ymul(c0[8 * j + 2], c0[8 * j + 3], hh[1], bh[1], z0[4 * j + 1]),
                  ymul(c0[8 * j + 4], c0[8 * j + 5], hh[0], bh[0], z0[4 * j + 2]), ymul(c0[8 * j + 6], c0[8 * j + 7], hh[1], bh[1], z0[4 * j + 3]), ep & 1);
        st_tagged(dst + 56 * 128 + j * 1024, ymul(c1[8 * j], c1[8 * j + 1], hh[2], bh[2], z1[4 * j]), ymul(c1[8 * j + 2], c1[8 * j + 3], hh[3], bh[3], z1[4 * j + 1]),
                  ymul(c1[8 * j + 4], c1[8 * j + 5], hh[2], bh[2], z1[4 * j + 2]), ymul(c1[8 * j + 6], c1[8 * j + 7], hh[3], bh[3], z1[4 * j + 3]), ep & 1);
        if (j == HINT_J) {
          __syncwarp();
          if (lane == 0) mbar_arrive(bars + 8 * (B_EA + 3));
          if (el) TS(54);
        }
      }
      if (el) TS(55);
    } else {
      {
        mbar_wait(bars + 8 * (B_XF + GATE_C), 0);
        const uint4* xr = reinterpret_cast<const uint4*>(p.x + (size_t)(rb * 128 + sl * 16 + (t128 >> 3)) * 512) + (t128 & 7);
        const uint4* wr = reinterpret_cast<const uint4*>(p.gate_w) + (t128 & 7);
        float s = 0.f;
#pragma unroll
        for (int i = 0; i < 8; i++) {
          const uint4 a = xr[8 * i], b = wr[8 * i];
          s = fmaf(bf_lo(a.x), bf_lo(b.x), s); s = fmaf(bf_hi(a.x), bf_hi(b.x), s); s = fmaf(bf_lo(a.y), bf_lo(b.y), s); s = fmaf(bf_hi(a.y), bf_hi(b.y), s);
          s = fmaf(bf_lo(a.z), bf_lo(b.z), s); s = fmaf(bf_hi(a.z), bf_hi(b.z), s); s = fmaf(bf_lo(a.w), bf_lo(b.w), s); s = fmaf(bf_hi(a.w), bf_hi(b.w), s);
        }
        s += __shfl_xor_sync(0xffffffffu, s, 1); s += __shfl_xor_sync(0xffffffffu, s, 2); s += __shfl_xor_sync(0xffffffffu, s, 4);
        if ((t128 & 7) == 0) g_gate[rb * 128 + sl * 16 + (t128 >> 3)] = __fdividef(1.f, 1.f + __expf(-s));
        __syncwarp();
        if (lane == 0) mbar_arrive(bars + 8 * B_GD);
      }
      uint32_t pk[32], pv[32];
      {
        float a0[64], a1[64];
        mbar_wait(bars + 8 * B_HO, 0);
        p1_tile<128>(a0, a1, 8, bars, el, B_HO + 1, 0, [](float (&d)[64], uint64_t a, uint64_t b, int sd) { wgmma_n128<1, 0>(d, a, b, sd); });
        if (el) TS(46);
#pragma unroll
        for (int i = 0; i < 32; i++) { pk[i] = phi2(a0[2 * i], a0[2 * i + 1]); pv[i] = pack_bf16(a1[2 * i], a1[2 * i + 1]); }
        if (el) TS(61);
      }
        mbar_wait(bars + 8 * B_SF1, 0);
        {
          if (el) TS(41);
          float dk[36];
          sts128(stg + (t128 >> 6) * 9216 + 8192 + (t128 & 63) * 16, 0x3f803f80u, 0x3f803f80u, 0x3f803f80u, 0x3f803f80u);
#pragma unroll
          for (int j = 0; j < 8; j++)
            stsm4(stg + (j >> 2) * 9216 + srow * 128 + (((2 * (j & 3) + (lane >> 4)) ^ (lane & 7)) << 4), pv[4 * j], pv[4 * j + 1], pv[4 * j + 2], pv[4 * j + 3]);
          fence_async_smem();
          named_bar(2, 128);
          wg_fence();
#pragma unroll
          for (int kk = 0; kk < 8; kk++)
            wgmma_n72_rs(dk, pk[4 * kk], pk[4 * kk + 1], pk[4 * kk + 2], pk[4 * kk + 3], desc_k128(OFF_STG + (kk >> 2) * 9216 + (kk & 3) * 32), kk != 0);
          wg_commit();
          if (el) TS(42);
          wg_wait<0>();
          reg_fence(dk);
          if (el) TS(43);
          const uint32_t ka = sb + OFF_KV + (w * 256 + 2 * q * 16 + g) * 4;
#pragma unroll
          for (int i = 0; i < 8; i++) {
            const float lo = (w & 1) ? dk[8 + i] : dk[i], hi = (w & 1) ? dk[24 + i] : dk[16 + i];
            asm volatile("st.shared.f32 [%0], %1;" ::"r"(ka + (((i >> 2) * 8 + (i & 1)) * 16 + (i & 2) * 4) * 4), "f"((w & 2) ? hi : lo) : "memory");
          }
          if (q == 0) {
            asm volatile("st.shared.f32 [%0], %1;" ::"r"(sb + OFF_KV + (1024 + w * 16 + g) * 4), "f"(dk[32]) : "memory");
            asm volatile("st.shared.f32 [%0], %1;" ::"r"(sb + OFF_KV + (1024 + w * 16 + g + 8) * 4), "f"(dk[34]) : "memory");
          }
          fence_async_smem();
          __syncwarp();
          if (lane == 0) mbar_arrive(bars + 8 * B_KVD);
          if (el) TS(47);
        }
      {
        float a0[64];
        mbar_wait(bars + 8 * (B_HO + 2), 0);
#pragma unroll 1
        for (int c = 0; c < 4; c++) {
          mbar_wait(bars + 8 * (B_F1 + 24 + c), 0);
          if (el) TS(64 + 24 + c);
          const uint32_t xa = 2 * c * SLOT, ra = (8 + c) * SLOT;
          reg_fence(a0);
          wg_fence();
#pragma unroll
          for (int kk = 0; kk < 8; kk++) {
            wgmma_n128<1, 0>(a0, desc_n128(ra + kk * 2048), desc_k128(xa + (kk >> 2) * SLOT + (kk & 3) * 32), kk != 0 || c != 0);
            if (kk == 1) {
              wg_commit();
              wg_wait<1>();
              if (el && c > 0) mbar_arrive(bars + 8 * (B_E1 + c - 1));
            }
          }
          wg_commit();
        }
        wg_wait<0>();
        reg_fence(a0);
        if (el) mbar_arrive(bars + 8 * (B_E1 + 3));
        if (el) TS(50);
#pragma unroll
        for (int i = 0; i < 8; i++)
          stsm4t(tbase + i * 2048, phi2(a0[8 * i], a0[8 * i + 1]), phi2(a0[8 * i + 2], a0[8 * i + 3]),
                 phi2(a0[8 * i + 4], a0[8 * i + 5]), phi2(a0[8 * i + 6], a0[8 * i + 7]));
        if (el) TS(51);
        mbar_wait(bars + 8 * B_GR, 0);
        float go[4];
#pragma unroll
        for (int i = 0; i < 4; i++) go[i] = ldg_cg32f(g_gate + rb * 128 + w * 16 + g + (i >> 1) * 64 + (i & 1) * 8);
        mbar_wait(bars + 8 * B_KVB, 0);
        if (el) TS(59);
        {
          asm volatile("ld.shared.u32 %0, [%1];" : "=r"(ep) : "r"(bars + 8 * W_EPOCH) : "memory");
          const float* kvs = g_kv + ((ep & 1) * 8 + sl) * 1088;
          const int r = lane;
          const float* src = kvs + w * 256 + ((r >> 4) * 8 + (r & 7)) * 16 + ((r >> 3) & 1) * 8;
          const float* zsrc = kvs + 1024 + w * 16 + ((r >> 3) & 1) * 8;
          const uint4 u0 = ldg_cg128(src), u1 = ldg_cg128(src + 4), u2 = ldg_cg128(zsrc), u3 = ldg_cg128(zsrc + 4);
          sts128(sb + OFF_KV + (w * 48 + r) * 16, pack_bf16(__uint_as_float(u0.x), __uint_as_float(u0.y)), pack_bf16(__uint_as_float(u0.z), __uint_as_float(u0.w)),
                 pack_bf16(__uint_as_float(u1.x), __uint_as_float(u1.y)), pack_bf16(__uint_as_float(u1.z), __uint_as_float(u1.w)));
          if (r < 16)
            sts128(sb + OFF_KV + (w * 48 + 32 + r) * 16, pack_bf16(__uint_as_float(u2.x), __uint_as_float(u2.y)), pack_bf16(__uint_as_float(u2.z), __uint_as_float(u2.w)),
                   pack_bf16(__uint_as_float(u3.x), __uint_as_float(u3.y)), pack_bf16(__uint_as_float(u3.z), __uint_as_float(u3.w)));
        }
        fence_async_smem();
        named_bar(2, 128);
        if (el) TS(52);
#pragma unroll 1
        for (int m = 0; m < 2; m++) {
          float d[4][12];
          const float g0 = m ? go[2] : go[0], g1 = m ? go[3] : go[1];
          wg_fence();
#pragma unroll
          for (int h = 0; h < 4; h++) wgmma_n24_z(d[h], desc_k128(OFF_STG + m * 8192 + h * 32), desc_k0(OFF_KV + h * 768));
          wg_commit();
          wg_wait<0>();
#pragma unroll
          for (int h = 0; h < 4; h++) {
            reg_fence(d[h]);
            const float i0 = g0 * rcp_fast(d[h][8] + 1e-6f), i1 = g1 * rcp_fast(d[h][10] + 1e-6f);
            st_tagged(g_of + ((rb * 2 + m) * 32 + sl * 4 + h) * 128 + t128, pack_bf16(d[h][0] * i0, d[h][1] * i0), pack_bf16(d[h][2] * i1, d[h][3] * i1),
                      pack_bf16(d[h][4] * i0, d[h][5] * i0), pack_bf16(d[h][6] * i1, d[h][7] * i1), ep & 1);
          }
        }
        if (el) TS(53);
      }
      uint32_t fo[128];
      mbar_wait(bars + 8 * (B_HO + 3), 0);
#pragma unroll
      for (int u = 0; u < 4; u++) {
        uint32_t spins = 0;
        while (true) {
#pragma unroll
          for (int kk = 8 * u; kk < 8 * u + 8; kk++) ld_frag(fo + 4 * kk, g_of + (r64 * 32 + kk) * 128 + t128);
          if (!__any_sync(0xffffffffu, stale8(fo + 32 * u, ep))) break;
          if (++spins > SPIN_LIMIT) TIMEOUT(30000);
          __nanosleep(300);
        }
      }
      mbar_wait(bars + 8 * (B_EA + 3), 0);
#pragma unroll
      for (int u = 0; u < 4; u++) {
        mbar_wait(bars + 8 * (B_F3 + u), 0);
        if (el) TS(128 + u);
        reg_fence(co);
        wg_fence();
#pragma unroll
        for (int kk = 0; kk < 8; kk++)
          wgmma_n128_rs(co, fo[32 * u + 4 * kk], fo[32 * u + 4 * kk + 1], fo[32 * u + 4 * kk + 2], fo[32 * u + 4 * kk + 3], desc_n128w(p2stage(p3idx(u)) + kk * 2048), kk != 0 || u != 0);
        wg_commit();
        wg_wait<1>();
        if (el && u > 0) mbar_arrive(bars + 8 * (u == 1 ? B_YR : B_E2 + 1 + u));
      }
      if (el) TS(37);
    }
    {
      const bool wg1 = warp >= 4;
      uint32_t fa[32], fb[32];
      auto step = [&](uint32_t (&f)[32], int j) {
        if (el) TS(232 + j);
        mbar_wait(bars + 8 * (B_FA + j), 0);
        if (el) TS(152 + j);
#pragma unroll
        for (int kk = 0; kk < 8; kk++) {
          const uint4 v = lds128(sb + yslot(j) + kk * 2048 + t128 * 16);
          f[4 * kk] = v.x; f[4 * kk + 1] = v.y; f[4 * kk + 2] = v.z; f[4 * kk + 3] = v.w;
        }
        mbar_wait(bars + 8 * (B_F3 + 4 + j), 0);
        uint32_t spins = 0;
        while (true) {
          if (spins) {
#pragma unroll
            for (int kk = 0; kk < 8; kk++) ld_frag(f + 4 * kk, g_yf + (r64 * 56 + j * 8 + kk) * 128 + t128);
          }
          if (!__any_sync(0xffffffffu, stale8(f, ep))) break;
          if (++spins > SPIN_LIMIT) TIMEOUT(30001 + j);
        }
        if (lane == 0 && j < 3) mbar_arrive(bars + 8 * (B_EA + j));
        if (el) TS(144 + j);
        if (el) TS(132 + j);
        const uint32_t st = p2stage(p3idx(4 + j));
        reg_fence(co);
        wg_fence();
#pragma unroll
        for (int kk = 0; kk < 8; kk++) {
          wgmma_n128_rs(co, f[4 * kk], f[4 * kk + 1], f[4 * kk + 2], f[4 * kk + 3], desc_n128w(st + kk * 2048), kk != 0 || j != 0);
          if (kk == 0) {
            wg_commit();
            wg_wait<1>();
            if (el && j >= 1 && j <= 3) mbar_arrive(bars + 8 * (B_E2 + (j == 1 ? 5 : j - 2)));
          }
        }
        wg_commit();
      };
#pragma unroll 1
      for (int j = wg1 ? 1 : 0; j < 7; j += 4) {
        step(fa, j);
        if (j + 2 < 7) step(fb, j + 2);
      }
      auto finish = [&](auto hc) {
        constexpr int H = hc;
        const uint32_t xw = sb + p2stage(4 + H) + t128 * 16, xr = sb + p2stage(5 - H) + t128 * 16;
        uint4 pp[8];
        if (H == 1) {
          named_bar(3, 256);
#pragma unroll
          for (int v = 0; v < 8; v++) pp[v] = lds128(xr + v * 2048);
        }
        wg_wait<0>();
        reg_fence(co);
        if (el) TS(38 + H);
#pragma unroll
        for (int v = 0; v < 8; v++) {
          const int i = 32 * (1 - H) + 4 * v;
          sts128(xw + v * 2048, __float_as_uint(co[i]), __float_as_uint(co[i + 1]), __float_as_uint(co[i + 2]), __float_as_uint(co[i + 3]));
        }
        asm volatile("bar.arrive %0, 256;" ::"n"(3 + H) : "memory");
        if (H == 0) {
          named_bar(4, 256);
#pragma unroll
          for (int v = 0; v < 8; v++) pp[v] = lds128(xr + v * 2048);
        }
        const uint32_t ob = sb + p2stage(4 + H) + SLOT;
#pragma unroll
        for (int v = 0; v < 4; v++) {
          const int i = 32 * H + 8 * v;
          const uint4 p0 = pp[2 * v], p1 = pp[2 * v + 1];
          stsm4(ob + srow * 128 + (((2 * v + (lane >> 4)) ^ (lane & 7)) << 4),
                pack_bf16(co[i] + __uint_as_float(p0.x), co[i + 1] + __uint_as_float(p0.y)), pack_bf16(co[i + 2] + __uint_as_float(p0.z), co[i + 3] + __uint_as_float(p0.w)),
                pack_bf16(co[i + 4] + __uint_as_float(p1.x), co[i + 5] + __uint_as_float(p1.y)), pack_bf16(co[i + 6] + __uint_as_float(p1.z), co[i + 7] + __uint_as_float(p1.w)));
        }
        __syncwarp();
#pragma unroll
        for (int j = 0; j < 4; j++) {
          const int r = w * 16 + j * 4 + (lane >> 3);
          const uint4 o = lds128(ob + r * 128 + (((lane & 7) ^ (r & 7)) << 4));
          *reinterpret_cast<uint4*>(p.out + (size_t)(r64 * 64 + r) * 512 + 128 * db + H * 64 + (lane & 7) * 8) = o;
        }
      };
      if (wg1) finish(IC<0>()); else finish(IC<1>());
      if (el) TS(wg1 ? 63 : 40);
    }
  }
}

typedef CUresult (*EncodeFn)(CUtensorMap*, CUtensorMapDataType, cuuint32_t, void*, const cuuint64_t*, const cuuint64_t*, const cuuint32_t*,
                             const cuuint32_t*, CUtensorMapInterleave, CUtensorMapSwizzle, CUtensorMapL2promotion, CUtensorMapFloatOOBfill);

#define PROMO CU_TENSOR_MAP_L2_PROMOTION_L2_128B
CUtensorMap make_map(EncodeFn enc, const void* base, uint64_t cols, uint64_t rows, uint32_t box_rows) {
  CUtensorMap m;
  cuuint64_t gd[2] = {cols, rows};
  cuuint64_t gs[1] = {cols * 2};
  cuuint32_t bd[2] = {64, box_rows};
  cuuint32_t es[2] = {1, 1};
  enc(&m, CU_TENSOR_MAP_DATA_TYPE_BFLOAT16, 2, const_cast<void*>(base), gd, gs, bd, es, CU_TENSOR_MAP_INTERLEAVE_NONE, CU_TENSOR_MAP_SWIZZLE_128B,
      PROMO, CU_TENSOR_MAP_FLOAT_OOB_FILL_NONE);
  return m;
}

CUtensorMap make_map3(EncodeFn enc, const void* base, uint64_t rows, uint64_t groups) {
  CUtensorMap m;
  cuuint64_t gd[3] = {512, rows, groups};
  cuuint64_t gs[2] = {1024, rows * 1024};
  cuuint32_t bd[3] = {64, 16, 8};
  cuuint32_t es[3] = {1, 1, 1};
  enc(&m, CU_TENSOR_MAP_DATA_TYPE_BFLOAT16, 3, const_cast<void*>(base), gd, gs, bd, es, CU_TENSOR_MAP_INTERLEAVE_NONE, CU_TENSOR_MAP_SWIZZLE_128B,
      PROMO, CU_TENSOR_MAP_FLOAT_OOB_FILL_NONE);
  return m;
}

}

extern "C" void kernel_launch(void* const* d_in, const int* in_sizes, int n_in, void* d_out, int out_size) {
  (void)in_sizes; (void)n_in; (void)out_size;
  static EncodeFn enc = nullptr;
  static int sms = 0;
  if (!enc) {
    void* fn = nullptr;
    cudaDriverEntryPointQueryResult qr;
    cudaGetDriverEntryPoint("cuTensorMapEncodeTiled", &fn, cudaEnableDefault, &qr);
    enc = (EncodeFn)fn;
    cudaDeviceGetAttribute(&sms, cudaDevAttrMultiProcessorCount, 0);
    cudaFuncSetAttribute(fused_kernel, cudaFuncAttributeMaxDynamicSharedMemorySize, SMEM_BYTES);
  }
  Params p;
  p.x = (const __nv_bfloat16*)d_in[0];
  p.wqkv = (const __nv_bfloat16*)d_in[1];
  p.wo = (const __nv_bfloat16*)d_in[2];
  p.w_in = (const __nv_bfloat16*)d_in[4];
  p.w_sp = (const __nv_bfloat16*)d_in[5];
  p.b_sp = (const __nv_bfloat16*)d_in[6];
  p.w_out = (const __nv_bfloat16*)d_in[7];
  p.out = (__nv_bfloat16*)d_out;
  p.gate_w = (const __nv_bfloat16*)d_in[8];
  const CUtensorMap tm_x = make_map(enc, p.x, 512, 2048, 128);
  const CUtensorMap tm_win = make_map(enc, p.w_in, 1792, 512, 64);
  const CUtensorMap tm_wqkv = make_map(enc, p.wqkv, 1536, 512, 64);
  const CUtensorMap tm_wsp = make_map(enc, p.w_sp, 2048, 2048, 128);
  const CUtensorMap tm_wo = make_map3(enc, p.wo, 16, 32);
  const CUtensorMap tm_wout = make_map3(enc, p.w_out, 64, 8);
  const CUtensorMap tm_wout2 = make_map3(enc, p.w_out + 512 * 512, 48, 8);
  fused_kernel<<<sms == 132 ? 132 : 128, 384, SMEM_BYTES, cudaStreamPerThread>>>(tm_x, tm_win, tm_wqkv, tm_wsp, tm_wo, tm_wout, tm_wout2, p);
}
```
